```python
import torch

def _softmax(x, axis=-1):
    return torch.softmax(x, dim=axis)
def _gelu(x):
    return torch.nn.functional.gelu(x, approximate="tanh")
def _silu(x):
    return torch.nn.functional.silu(x)
def _sigmoid(x):
    return torch.sigmoid(x)
def _layernorm(x, axis=-1, eps=1e-5):
    m = x.mean(dim=axis, keepdim=True)
    v = x.var(dim=axis, keepdim=True, unbiased=False)
    return (x - m) / torch.sqrt(v + eps)
def _scatter_add(tgt, idx, src, axis=0):
    return tgt.clone().index_add_(axis, idx, src)
def _segment_sum(src, seg, n):
    out = torch.zeros((n,) + src.shape[1:], dtype=src.dtype)
    return out.index_add_(0, seg, src)
def _pad(x, pw):
    flat = tuple(v for pair in reversed(pw) for v in pair)
    return torch.nn.functional.pad(x, flat)

kernel_name = 'parallel_sum__linear_attn_block__glu_gated_geglu__prompt'

def setup_inputs():

    _w = (lambda a: (lambda t: t.to(torch.bfloat16) if t.is_floating_point() else t)(torch.as_tensor(a)))
    def _A_setup():
        B, S, D = 1, 2048, 512
        return {
            "x": _w((lambda *s: torch.randn(*s, dtype=torch.bfloat16) * 0.05)(B, S, D)),
            "wqkv": _w((lambda *s: torch.randn(*s, dtype=torch.bfloat16) * 0.1)(D, 3 * D)),
            "wo": _w((lambda *s: torch.randn(*s, dtype=torch.bfloat16) * 0.05)(D, D)),
        }
    _A_in = _A_setup()

    def _B_setup():
        B, S, Dm, Df = 1, 2048, 512, 1376
        return {
            "x": _w((lambda *s: torch.randn(*s, dtype=torch.bfloat16) * 0.05)(B, S, Dm)),
            "w_gate": _w((lambda *s: torch.randn(*s, dtype=torch.bfloat16) * 0.4)(Dm, Df) * (Dm ** -0.5)),
            "w_up": _w((lambda *s: torch.randn(*s, dtype=torch.bfloat16) * 0.4)(Dm, Df) * (Dm ** -0.5)),
            "w_down": _w((lambda *s: torch.randn(*s, dtype=torch.bfloat16) * 0.4)(Df, Dm) * (Df ** -0.5)),
        }
    _B_in = _B_setup()

    return {
        "A_x": _A_in["x"],
        "A_wqkv": _A_in["wqkv"],
        "A_wo": _A_in["wo"],
        "B_x": _B_in["x"],
        "B_w_gate": _B_in["w_gate"],
        "B_w_up": _B_in["w_up"],
        "B_w_down": _B_in["w_down"],
    }

def reference(A_x, A_wqkv, A_wo, B_x, B_w_gate, B_w_up, B_w_down):
    def _A_ref(x, wqkv, wo):
        B, S, D = x.shape
        H = 32; Dh = D // H
        qkv = (lambda x, *d: x.permute(*d))((x @ wqkv).reshape(B, S, 3, H, Dh), 2, 0, 3, 1, 4)
        q, k, v = qkv[0], qkv[1], qkv[2]
        phi = lambda t: torch.where(t > 0, t + 1, torch.exp(t)) + 1e-6
        pq, pk = phi(q), phi(k)
        kv = torch.einsum("bhsd,bhse->bhde", pk, v)
        z = torch.einsum("bhsd->bhd", pk)
        num = torch.einsum("bhqd,bhde->bhqe", pq, kv)
        den = torch.einsum("bhqd,bhd->bhq", pq, z)[..., None] + 1e-6
        o = num / den
        return (lambda x, *d: x.permute(*d))(o, 0, 2, 1, 3).reshape(B, S, D) @ wo

    def _B_ref(x, w_gate, w_up, w_down):
        g = torch.einsum("bsd,df->bsf", x, w_gate)
        u = torch.einsum("bsd,df->bsf", x, w_up)
        h = _gelu(g) * u
        return torch.einsum("bsf,fd->bsd", h, w_down)

    x = A_x
    xn = _layernorm(x, axis=-1)
    return x + _A_ref(xn, A_wqkv, A_wo) + _B_ref(xn, B_w_gate, B_w_up, B_w_down)
```

```cpp
#include <cuda_runtime.h>
#include <cuda.h>
#include <cuda_bf16.h>
#include <stdint.h>

namespace {

constexpr int S_ = 2048, D_ = 512, F_ = 1376;
constexpr int FS = 176;
constexpr int NCTA = 128;
constexpr int WSLOT = 16384, ASLOT = 8192;
#define LAG_KB 4
#define XPF_W 0
#define PREP_WAIT_P 9
#define WHOLD_W 1
#define WHOLD 3
#define WHOLD_P 2
#define PEEK_AT 2
#define L2PROMO CU_TENSOR_MAP_L2_PROMOTION_L2_128B
#define FLAG_AT 8
#define FETCH_B_AT 14
constexpr int NW = 8, NA = 6;
constexpr int OFF_W = 0;
constexpr int OFF_A = NW * WSLOT;
constexpr int OFF_BAR = OFF_A + 2 * NA * ASLOT;
constexpr int B_WFULL = 0, B_WEMPTY = 8, B_XFULL = 16  , B_W0DONE = 17, B_X1GO = 18, B_X1GOT = 19, B_AFULL = 24  , B_AEMPTY = 36  ,
              B_BLK = 48  , B_KVDONE = 56  , B_KVRDY = 58, B_LAG = 59, B_EPOCH = 60, B_KVLD = 61, B_PART = 62, B_X0DONE = 63, B_COUNT = 64;
constexpr int OFF_ONES = OFF_BAR + 640;
constexpr int OFF_EPOCH = OFF_ONES + 128;
constexpr int SMEM_BYTES = OFF_EPOCH + 16;

__device__ uint4 g_a2[32 * 8 * 3 * (ASLOT / 16)];
__device__ uint4 g_h2[32 * 8 * 3 * 128];
__device__ uint4 g_part[16 * 8 * 8 * 128];
__device__ float g_kv[2][32 * 272];
__device__ uint4 g_flag_a2[32 * 8];
__device__ unsigned g_cnt_kv[8 * 32];
__device__ uint4 g_flag_part[16 * 8 * 4 * 2];
__device__ unsigned g_done;
#define DBGL(i)
#define DBG(role, idx)
#define DBGW(role, idx)
#define DBGT(role, idx)
#define DBGG(role)

__device__ __forceinline__ uint32_t smem_u32(const void* p) { return (uint32_t)__cvta_generic_to_shared(p); }
__device__ __forceinline__ void mbar_init(uint32_t bar, uint32_t cnt) {
  asm volatile("mbarrier.init.shared::cta.b64 [%0], %1;" ::"r"(bar), "r"(cnt));
}
__device__ __forceinline__ void mbar_expect_tx(uint32_t bar, uint32_t bytes) {
  asm volatile("mbarrier.arrive.expect_tx.shared::cta.b64 _, [%0], %1;" ::"r"(bar), "r"(bytes) : "memory");
}
__device__ __forceinline__ void mbar_arrive(uint32_t bar) {
  asm volatile("mbarrier.arrive.shared::cta.b64 _, [%0];" ::"r"(bar) : "memory");
}
__device__ __forceinline__ void mbar_arrive_cluster(uint32_t bar_cluster_addr) {
  asm volatile("mbarrier.arrive.shared::cluster.b64 _, [%0];" ::"r"(bar_cluster_addr) : "memory");
}
__device__ __forceinline__ void mbar_wait(uint32_t bar, uint32_t parity) {
  asm volatile("{\n.reg .pred p, q;\n.reg .u32 n;\n"
               "mbarrier.try_wait.parity.shared::cta.b64 p, [%0], %1;\n"
               "@p bra WAIT_DONE;\n"
               "mov.u32 n, 0;\n"
               "WAIT_LOOP:\n"
               "mbarrier.try_wait.parity.shared::cta.b64 p, [%0], %1;\n"
               "add.u32 n, n, 1;\nsetp.gt.u32 q, n, 65536;\nor.pred p, p, q;\n"
               "@!p bra WAIT_LOOP;\n"
               "WAIT_DONE:\n}\n" ::"r"(bar), "r"(parity) : "memory");
}
__device__ __forceinline__ void mbar_wait_loop(uint32_t bar, uint32_t parity) {
  asm volatile("{\n.reg .pred p, q;\n.reg .u32 n;\nmov.u32 n, 0;\n"
               "WAIT_LOOP:\n"
               "mbarrier.try_wait.parity.shared::cta.b64 p, [%0], %1;\n"
               "add.u32 n, n, 1;\nsetp.gt.u32 q, n, 65536;\nor.pred p, p, q;\n"
               "@!p bra WAIT_LOOP;\n}\n" ::"r"(bar), "r"(parity) : "memory");
}
#define PEEK(bar, par) asm volatile("mbarrier.try_wait.parity.shared::cta.b64 PK, [%0], %1;" ::"r"(bar), "r"(par) : "memory")
#define PEEK_AND(bar, par) asm volatile("{\n.reg .pred t;\nmbarrier.try_wait.parity.shared::cta.b64 t, [%0], %1;\nand.pred PK, PK, t;\n}\n" ::"r"(bar), "r"(par) : "memory")
#define PEEKWAIT(bar, par)                                                                                   \
  asm volatile("{\n.reg .pred p, q;\n.reg .u32 n;\n@PK bra WD;\nmov.u32 n, 0;\nWL:\n"                     \
               "mbarrier.try_wait.parity.shared::cta.b64 p, [%0], %1;\n"                                     \
               "add.u32 n, n, 1;\nsetp.gt.u32 q, n, 65536;\nor.pred p, p, q;\n@!p bra WL;\nWD:\n}\n" ::"r"(bar), "r"(par) : "memory")
#define PEEKWAIT2(bar, par, bar2, par2)                                                                      \
  asm volatile("{\n.reg .pred p, q;\n.reg .u32 n;\n@PK bra WD;\nmov.u32 n, 0;\nWL:\n"                     \
               "mbarrier.try_wait.parity.shared::cta.b64 p, [%0], %1;\n"                                     \
               "mbarrier.try_wait.parity.shared::cta.b64 q, [%2], %3;\nand.pred p, p, q;\n"                  \
               "add.u32 n, n, 1;\nsetp.gt.u32 q, n, 65536;\nor.pred p, p, q;\n@!p bra WL;\nWD:\n}\n" ::"r"(bar), "r"(par), "r"(bar2), "r"(par2) : "memory")
__device__ __forceinline__ uint32_t mapa(uint32_t addr, uint32_t cta) {
  uint32_t r;
  asm volatile("mapa.shared::cluster.u32 %0, %1, %2;" : "=r"(r) : "r"(addr), "r"(cta));
  return r;
}
__device__ __forceinline__ bool elect_one() {
  uint32_t p;
  asm volatile("{\n.reg .pred p;\nelect.sync _|p, 0xffffffff;\nselp.u32 %0, 1, 0, p;\n}\n" : "=r"(p));
  return p != 0;
}
__device__ __forceinline__ void tma2d(uint32_t dst, const CUtensorMap* m, int c0, int c1, uint32_t bar) {
  asm volatile("cp.async.bulk.tensor.2d.shared::cluster.global.mbarrier::complete_tx::bytes [%0], [%1, {%3, %4}], [%2];"
               ::"r"(dst), "l"(m), "r"(bar), "r"(c0), "r"(c1) : "memory");
}
__device__ __forceinline__ void tma2d_mc(uint32_t dst, const CUtensorMap* m, int c0, int c1, uint32_t bar, uint16_t mask) {
  asm volatile("cp.async.bulk.tensor.2d.shared::cluster.global.mbarrier::complete_tx::bytes.multicast::cluster [%0], [%1, {%3, %4}], [%2], %5;"
               ::"r"(dst), "l"(m), "r"(bar), "r"(c0), "r"(c1), "h"(mask) : "memory");
}
__device__ __forceinline__ void bulk_load(uint32_t dst, const void* src, uint32_t bytes, uint32_t bar) {
  asm volatile("cp.async.bulk.shared::cluster.global.mbarrier::complete_tx::bytes [%0], [%1], %2, [%3];"
               ::"r"(dst), "l"(src), "r"(bytes), "r"(bar) : "memory");
}
__device__ __forceinline__ void bulk_store(void* dst, uint32_t src, uint32_t bytes) {
  asm volatile("cp.async.bulk.global.shared::cta.bulk_group [%0], [%1], %2;" ::"l"(dst), "r"(src), "r"(bytes) : "memory");
  asm volatile("cp.async.bulk.commit_group;" ::: "memory");
}
__device__ __forceinline__ void bulk_wait_all() { asm volatile("cp.async.bulk.wait_group 0;" ::: "memory"); }
__device__ __forceinline__ void fence_async_smem() { asm volatile("fence.proxy.async.shared::cta;" ::: "memory"); }
__device__ __forceinline__ void fence_async_global() { asm volatile("fence.proxy.async.global;" ::: "memory"); }
__device__ __forceinline__ void tma2d_store(const CUtensorMap* m, uint32_t src, int c0, int c1) {
  asm volatile("cp.async.bulk.tensor.2d.global.shared::cta.bulk_group [%0, {%2, %3}], [%1];" ::"l"(m), "r"(src), "r"(c0), "r"(c1) : "memory");
}
__device__ __forceinline__ unsigned ld_acquire(const unsigned* p) {
  unsigned v;
  asm volatile("ld.acquire.gpu.global.u32 %0, [%1];" : "=r"(v) : "l"(p) : "memory");
  return v;
}
__device__ __forceinline__ unsigned ld_relaxed(const unsigned* p) {
  unsigned v;
  asm volatile("ld.relaxed.gpu.global.u32 %0, [%1];" : "=r"(v) : "l"(p) : "memory");
  return v;
}
__device__ __forceinline__ void st_release(unsigned* p, unsigned v) {
  asm volatile("st.release.gpu.global.u32 [%0], %1;" ::"l"(p), "r"(v) : "memory");
}
__device__ __forceinline__ void red_release_add(unsigned* p, unsigned v) {
  asm volatile("red.release.gpu.global.add.u32 [%0], %1;" ::"l"(p), "r"(v) : "memory");
}
__device__ __forceinline__ void poll_ge(const unsigned* p, unsigned target) {
  uint32_t n = 0;
  while ((int)(ld_acquire(p) - target) < 0) {
    if (++n > (1u << 16)) break;
  }
}
__device__ __forceinline__ void ldsm4(uint32_t* r, uint32_t addr) {
  asm volatile("ldmatrix.sync.aligned.m8n8.x4.shared.b16 {%0, %1, %2, %3}, [%4];"
               : "=r"(r[0]), "=r"(r[1]), "=r"(r[2]), "=r"(r[3]) : "r"(addr) : "memory");
}
__device__ __forceinline__ void stsm4(uint32_t addr, uint32_t a, uint32_t b, uint32_t c, uint32_t d) {
  asm volatile("stmatrix.sync.aligned.m8n8.x4.shared.b16 [%0], {%1, %2, %3, %4};" ::"r"(addr), "r"(a), "r"(b), "r"(c), "r"(d) : "memory");
}
__device__ __forceinline__ void mma_rowsum(float* c, const uint32_t* a) {
  asm volatile("mma.sync.aligned.m16n8k16.row.col.f32.bf16.bf16.f32 {%0, %1, %2, %3}, {%4, %5, %6, %7}, {%8, %8}, {%0, %1, %2, %3};"
               : "+f"(c[0]), "+f"(c[1]), "+f"(c[2]), "+f"(c[3]) : "r"(a[0]), "r"(a[1]), "r"(a[2]), "r"(a[3]), "r"(0x3F803F80u));
}
__device__ __forceinline__ uint32_t pack_bf16(float lo, float hi) {
  uint32_t r;
  asm("cvt.rn.bf16x2.f32 %0, %1, %2;" : "=r"(r) : "f"(hi), "f"(lo));
  return r;
}
__device__ __forceinline__ float bf_lo(uint32_t w) { return __uint_as_float(w << 16); }
__device__ __forceinline__ float bf_hi(uint32_t w) { return __uint_as_float(w & 0xffff0000u); }
__device__ __forceinline__ uint32_t bf2_fma(uint32_t a, uint32_t b, uint32_t c) {
  uint32_t r;
  asm("fma.rn.bf16x2 %0, %1, %2, %3;" : "=r"(r) : "r"(a), "r"(b), "r"(c));
  return r;
}
__device__ __forceinline__ uint4 ld_relaxed_u4(const void* p) {
  uint4 v;
  asm volatile("ld.relaxed.gpu.global.v4.u32 {%0, %1, %2, %3}, [%4];" : "=r"(v.x), "=r"(v.y), "=r"(v.z), "=r"(v.w) : "l"(p) : "memory");
  return v;
}
__device__ __forceinline__ float ex2f(float x) { float r; asm("ex2.approx.ftz.f32 %0, %1;" : "=f"(r) : "f"(x)); return r; }
__device__ __forceinline__ float tanhf_fast(float x) { float r; asm("tanh.approx.f32 %0, %1;" : "=f"(r) : "f"(x)); return r; }
__device__ __forceinline__ float rcpf(float x) { float r; asm("rcp.approx.ftz.f32 %0, %1;" : "=f"(r) : "f"(x)); return r; }
#define WG_FENCE() asm volatile("wgmma.fence.sync.aligned;" ::: "memory")
#define WG_COMMIT() asm volatile("wgmma.commit_group.sync.aligned;" ::: "memory")
#define WG_WAIT(n) asm volatile("wgmma.wait_group.sync.aligned %0;" ::"n"(n) : "memory")

constexpr uint32_t SMEM0 = 1024;
__host__ __device__ constexpr uint64_t mkdesc(uint32_t off, uint32_t lbo, uint32_t sbo, uint32_t swz) {
  return (uint64_t)((SMEM0 + off) >> 4) | ((uint64_t)(lbo >> 4) << 16) | ((uint64_t)(sbo >> 4) << 32) | ((uint64_t)swz << 62);
}
__host__ __device__ constexpr uint64_t desc_mn(uint32_t off) { return mkdesc(off, 8192, 1024, 1); }
__host__ __device__ constexpr uint64_t desc_k(uint32_t off) { return mkdesc(off, 16, 1024, 1); }

__device__ __forceinline__ void wgmma_rs_n128(float (&d)[64], const uint32_t* a, uint64_t descB, int scaleD) {
  asm volatile("{\n.reg .pred p;\nsetp.ne.b32 p, %69, 0;\n"
    "wgmma.mma_async.sync.aligned.m64n128k16.f32.bf16.bf16 {%0, %1, %2, %3, %4, %5, %6, %7, %8, %9, %10, %11, %12, %13, %14, %15, %16, %17, %18, %19, %20, %21, %22, %23, %24, %25, %26, %27, %28, %29, %30, %31, %32, %33, %34, %35, %36, %37, %38, %39, %40, %41, %42, %43, %44, %45, %46, %47, %48, %49, %50, %51, %52, %53, %54, %55, %56, %57, %58, %59, %60, %61, %62, %63}, {%64, %65, %66, %67}, %68, p, 1, 1, 1;\n}\n"
    : "+f"(d[0]), "+f"(d[1]), "+f"(d[2]), "+f"(d[3]), "+f"(d[4]), "+f"(d[5]), "+f"(d[6]), "+f"(d[7]), "+f"(d[8]), "+f"(d[9]), "+f"(d[10]), "+f"(d[11]), "+f"(d[12]), "+f"(d[13]), "+f"(d[14]), "+f"(d[15]), "+f"(d[16]), "+f"(d[17]), "+f"(d[18]), "+f"(d[19]), "+f"(d[20]), "+f"(d[21]), "+f"(d[22]), "+f"(d[23]), "+f"(d[24]), "+f"(d[25]), "+f"(d[26]), "+f"(d[27]), "+f"(d[28]), "+f"(d[29]), "+f"(d[30]), "+f"(d[31]), "+f"(d[32]), "+f"(d[33]), "+f"(d[34]), "+f"(d[35]), "+f"(d[36]), "+f"(d[37]), "+f"(d[38]), "+f"(d[39]), "+f"(d[40]), "+f"(d[41]), "+f"(d[42]), "+f"(d[43]), "+f"(d[44]), "+f"(d[45]), "+f"(d[46]), "+f"(d[47]), "+f"(d[48]), "+f"(d[49]), "+f"(d[50]), "+f"(d[51]), "+f"(d[52]), "+f"(d[53]), "+f"(d[54]), "+f"(d[55]), "+f"(d[56]), "+f"(d[57]), "+f"(d[58]), "+f"(d[59]), "+f"(d[60]), "+f"(d[61]), "+f"(d[62]), "+f"(d[63])
    : "r"(a[0]), "r"(a[1]), "r"(a[2]), "r"(a[3]), "l"(descB), "r"(scaleD));
}
__device__ __forceinline__ void wgmma_rs_n64(float (&d)[32], const uint32_t* a, uint64_t descB, int scaleD) {
  asm volatile("{\n.reg .pred p;\nsetp.ne.b32 p, %37, 0;\n"
    "wgmma.mma_async.sync.aligned.m64n64k16.f32.bf16.bf16 {%0, %1, %2, %3, %4, %5, %6, %7, %8, %9, %10, %11, %12, %13, %14, %15, %16, %17, %18, %19, %20, %21, %22, %23, %24, %25, %26, %27, %28, %29, %30, %31}, {%32, %33, %34, %35}, %36, p, 1, 1, 1;\n}\n"
    : "+f"(d[0]), "+f"(d[1]), "+f"(d[2]), "+f"(d[3]), "+f"(d[4]), "+f"(d[5]), "+f"(d[6]), "+f"(d[7]), "+f"(d[8]), "+f"(d[9]), "+f"(d[10]), "+f"(d[11]), "+f"(d[12]), "+f"(d[13]), "+f"(d[14]), "+f"(d[15]), "+f"(d[16]), "+f"(d[17]), "+f"(d[18]), "+f"(d[19]), "+f"(d[20]), "+f"(d[21]), "+f"(d[22]), "+f"(d[23]), "+f"(d[24]), "+f"(d[25]), "+f"(d[26]), "+f"(d[27]), "+f"(d[28]), "+f"(d[29]), "+f"(d[30]), "+f"(d[31])
    : "r"(a[0]), "r"(a[1]), "r"(a[2]), "r"(a[3]), "l"(descB), "r"(scaleD));
}
__device__ __forceinline__ void wgmma_rs_n48(float (&d)[24], const uint32_t* a, uint64_t descB, int scaleD) {
  asm volatile("{\n.reg .pred p;\nsetp.ne.b32 p, %29, 0;\n"
    "wgmma.mma_async.sync.aligned.m64n48k16.f32.bf16.bf16 {%0, %1, %2, %3, %4, %5, %6, %7, %8, %9, %10, %11, %12, %13, %14, %15, %16, %17, %18, %19, %20, %21, %22, %23}, {%24, %25, %26, %27}, %28, p, 1, 1, 1;\n}\n"
    : "+f"(d[0]), "+f"(d[1]), "+f"(d[2]), "+f"(d[3]), "+f"(d[4]), "+f"(d[5]), "+f"(d[6]), "+f"(d[7]), "+f"(d[8]), "+f"(d[9]), "+f"(d[10]), "+f"(d[11]), "+f"(d[12]), "+f"(d[13]), "+f"(d[14]), "+f"(d[15]), "+f"(d[16]), "+f"(d[17]), "+f"(d[18]), "+f"(d[19]), "+f"(d[20]), "+f"(d[21]), "+f"(d[22]), "+f"(d[23])
    : "r"(a[0]), "r"(a[1]), "r"(a[2]), "r"(a[3]), "l"(descB), "r"(scaleD));
}
__device__ __forceinline__ void wgmma_ss_n128(float (&d)[64], uint64_t descA, uint64_t descB, int scaleD) {
  asm volatile("{\n.reg .pred p;\nsetp.ne.b32 p, %66, 0;\n"
    "wgmma.mma_async.sync.aligned.m64n128k16.f32.bf16.bf16 {%0, %1, %2, %3, %4, %5, %6, %7, %8, %9, %10, %11, %12, %13, %14, %15, %16, %17, %18, %19, %20, %21, %22, %23, %24, %25, %26, %27, %28, %29, %30, %31, %32, %33, %34, %35, %36, %37, %38, %39, %40, %41, %42, %43, %44, %45, %46, %47, %48, %49, %50, %51, %52, %53, %54, %55, %56, %57, %58, %59, %60, %61, %62, %63}, %64, %65, p, 1, 1, 0, 1;\n}\n"
    : "+f"(d[0]), "+f"(d[1]), "+f"(d[2]), "+f"(d[3]), "+f"(d[4]), "+f"(d[5]), "+f"(d[6]), "+f"(d[7]), "+f"(d[8]), "+f"(d[9]), "+f"(d[10]), "+f"(d[11]), "+f"(d[12]), "+f"(d[13]), "+f"(d[14]), "+f"(d[15]), "+f"(d[16]), "+f"(d[17]), "+f"(d[18]), "+f"(d[19]), "+f"(d[20]), "+f"(d[21]), "+f"(d[22]), "+f"(d[23]), "+f"(d[24]), "+f"(d[25]), "+f"(d[26]), "+f"(d[27]), "+f"(d[28]), "+f"(d[29]), "+f"(d[30]), "+f"(d[31]), "+f"(d[32]), "+f"(d[33]), "+f"(d[34]), "+f"(d[35]), "+f"(d[36]), "+f"(d[37]), "+f"(d[38]), "+f"(d[39]), "+f"(d[40]), "+f"(d[41]), "+f"(d[42]), "+f"(d[43]), "+f"(d[44]), "+f"(d[45]), "+f"(d[46]), "+f"(d[47]), "+f"(d[48]), "+f"(d[49]), "+f"(d[50]), "+f"(d[51]), "+f"(d[52]), "+f"(d[53]), "+f"(d[54]), "+f"(d[55]), "+f"(d[56]), "+f"(d[57]), "+f"(d[58]), "+f"(d[59]), "+f"(d[60]), "+f"(d[61]), "+f"(d[62]), "+f"(d[63])
    : "l"(descA), "l"(descB), "r"(scaleD));
}
__device__ __forceinline__ void wgmma_rs_n24(float (&d)[12], const uint32_t* a, uint64_t descB, int scaleD) {
  asm volatile("{\n.reg .pred p;\nsetp.ne.b32 p, %17, 0;\n"
    "wgmma.mma_async.sync.aligned.m64n24k16.f32.bf16.bf16 {%0, %1, %2, %3, %4, %5, %6, %7, %8, %9, %10, %11}, {%12, %13, %14, %15}, %16, p, 1, 1, 1;\n}\n"
    : "+f"(d[0]), "+f"(d[1]), "+f"(d[2]), "+f"(d[3]), "+f"(d[4]), "+f"(d[5]), "+f"(d[6]), "+f"(d[7]), "+f"(d[8]), "+f"(d[9]), "+f"(d[10]), "+f"(d[11])
    : "r"(a[0]), "r"(a[1]), "r"(a[2]), "r"(a[3]), "l"(descB), "r"(scaleD));
}
__device__ __forceinline__ void wgmma_st_n64(float (&d)[32], uint64_t descA, uint64_t descB, int scaleD) {
  asm volatile("{\n.reg .pred p;\nsetp.ne.b32 p, %34, 0;\n"
    "wgmma.mma_async.sync.aligned.m64n64k16.f32.bf16.bf16 {%0, %1, %2, %3, %4, %5, %6, %7, %8, %9, %10, %11, %12, %13, %14, %15, %16, %17, %18, %19, %20, %21, %22, %23, %24, %25, %26, %27, %28, %29, %30, %31}, %32, %33, p, 1, 1, 1, 1;\n}\n"
    : "+f"(d[0]), "+f"(d[1]), "+f"(d[2]), "+f"(d[3]), "+f"(d[4]), "+f"(d[5]), "+f"(d[6]), "+f"(d[7]), "+f"(d[8]), "+f"(d[9]), "+f"(d[10]), "+f"(d[11]), "+f"(d[12]), "+f"(d[13]), "+f"(d[14]), "+f"(d[15]), "+f"(d[16]), "+f"(d[17]), "+f"(d[18]), "+f"(d[19]), "+f"(d[20]), "+f"(d[21]), "+f"(d[22]), "+f"(d[23]), "+f"(d[24]), "+f"(d[25]), "+f"(d[26]), "+f"(d[27]), "+f"(d[28]), "+f"(d[29]), "+f"(d[30]), "+f"(d[31])
    : "l"(descA), "l"(descB), "r"(scaleD));
}
__device__ __forceinline__ void wgmma_st_n8(float (&d)[4], uint64_t descA, uint64_t descB, int scaleD) {
  asm volatile("{\n.reg .pred p;\nsetp.ne.b32 p, %6, 0;\n"
    "wgmma.mma_async.sync.aligned.m64n8k16.f32.bf16.bf16 {%0, %1, %2, %3}, %4, %5, p, 1, 1, 1, 1;\n}\n"
    : "+f"(d[0]), "+f"(d[1]), "+f"(d[2]), "+f"(d[3])
    : "l"(descA), "l"(descB), "r"(scaleD));
}

__device__ __forceinline__ float phi(float a, float rl) {
  const float u = a * rl;
  return fmaf(fmaxf(u, 1.4426950e-6f), 0.6931471805599453f, ex2f(fminf(u, 0.f)));
}
constexpr float GC = 0.32920349f, GK = 2.42368195f, GV = 1.51881743f;
__device__ __forceinline__ float geglu2(float sg, float v) {
  const float th = tanhf_fast(sg * fmaf(sg, sg, GK));
  const float gv = sg * v;
  return fmaf(gv, th, gv);
}

struct Params {
  const char *x, *wqkv, *wo, *wg, *wu, *wd;
};
__device__ __forceinline__ void l2_prefetch(const void* p, uint32_t bytes) {
  asm volatile("cp.async.bulk.prefetch.L2.global [%0], %1;" ::"l"(p), "r"(bytes) : "memory");
}

__device__ __forceinline__ unsigned get_epoch(uint32_t sb) {
  mbar_wait(sb + OFF_BAR + B_EPOCH * 8, 0);
  unsigned e;
  asm volatile("ld.shared.b32 %0, [%1];" : "=r"(e) : "r"(sb + OFF_EPOCH) : "memory");
  return e;
}
__device__ __forceinline__ void store_block(uint4* gdst, uint32_t ssrc, unsigned* flag, unsigned tag) {
  bulk_store(gdst, ssrc, ASLOT);
  bulk_wait_all();
  fence_async_global();
  st_release(flag, tag);
}
__global__ void __cluster_dims__(2, 1, 1) __launch_bounds__(384, 1)
fused_kernel(const __grid_constant__ CUtensorMap tm_x, const __grid_constant__ CUtensorMap tm_qkv,
             const __grid_constant__ CUtensorMap tm_g, const __grid_constant__ CUtensorMap tm_u,
             const __grid_constant__ CUtensorMap tm_o, const __grid_constant__ CUtensorMap tm_d,
             const __grid_constant__ CUtensorMap tm_d48, const __grid_constant__ CUtensorMap tm_out, const Params prm) {
  asm volatile(".reg .pred PK;");
  extern __shared__ __align__(1024) uint8_t smem_raw[];
  const uint32_t sb = smem_u32(smem_raw);
  if ((sb & 0xFFFFFFu) != SMEM0) return;
  const uint32_t bars = sb + OFF_BAR;
  const int tid = threadIdx.x, lane = tid & 31;
  if (tid == 256) {
    l2_prefetch(prm.x + blockIdx.x * 16384, 16384);
  }
  const int wid = __shfl_sync(0xffffffffu, tid >> 5, 0);
  const uint32_t rank = blockIdx.x & 1;
  const int cl = blockIdx.x >> 1;
  int mp, j;
  if (cl < 4) { mp = 0; j = 4 + cl; }
  else if (cl < 36) { mp = (cl - 4) & 7; j = (cl - 4) >> 3; }
  else { mp = 1 + (cl - 36) % 7; j = 4 + (cl - 36) / 7; }
  const int m = mp * 2 + (int)rank;
  const int kap = j >> 2, nu = j & 3;
  auto peer = [&](int p) { return (j & 4) + p + (p >= nu ? 1 : 0); };
  if (tid == 0) { DBGT(0, 30); }
  if (tid == 352) { DBGL(0); }

  auto load_x = [&](int w, int wq, int p0, int p1) {
    const int rl = wq * 16 + (lane >> 4), c = lane & 15;
    const char* src = prm.x + (size_t)(m * 128 + (w == 0 ? 1 - kap : kap) * 64 + rl) * 1024 + c * 16;
#pragma unroll
    for (int p = p0; p < p1; p++) {
      const uint32_t base = (p < 3 ? sb + OFF_A + (w * NA + 2 * p) * ASLOT : sb + OFF_W + (7 - w) * WSLOT) + (c >> 3) * ASLOT;
#pragma unroll
      for (int i = 0; i < 8; i++) {
        const int r = rl + 2 * i;
        asm volatile("cp.async.cg.shared.global [%0], [%1], 16;" ::"r"(base + r * 128 + (((c ^ r) & 7) << 4)), "l"(src + i * 2048 + p * 256) : "memory");
      }
      asm volatile("cp.async.commit_group;" ::: "memory");
    }
  };
  if (wid < 8) asm volatile("barrier.cluster.arrive.relaxed.aligned;" ::: "memory");
  if (wid < 4) {
    DBGW(0, 27);
    load_x(0, wid, 0, 4);
    DBGW(0, 28);
  } else if (wid < 8) {
    load_x(1, wid - 4, 0, 4);
  } else if (wid == 8) {
    if (lane < 8) {
      const CUtensorMap* tms[8] = {&tm_qkv, &tm_g, &tm_u, &tm_o, &tm_d, &tm_d48, &tm_x, &tm_out};
      const CUtensorMap* t = tms[0];
#pragma unroll
      for (int i = 1; i < 8; i++) t = lane == i ? tms[i] : t;
      asm volatile("prefetch.tensormap [%0];" ::"l"(t) : "memory");
    }
  } else if (wid == 9 || wid == 10) {
    if (elect_one()) {
#pragma unroll
      for (int i = 0; i < B_COUNT; i++) {
        const uint32_t cnt = (i >= B_WEMPTY && i < B_XFULL) ? 16 : ((i >= B_AEMPTY && i < B_KVRDY) || i == B_LAG || i == B_W0DONE || i == B_X0DONE || i == B_X1GO || i == B_X1GOT) ? 4 : 1;
        if ((i < 36) == (wid == 9)) mbar_init(bars + i * 8, cnt);
      }
      asm volatile("fence.mbarrier_init.release.cluster;" ::: "memory");
    }
    __syncwarp();
  } else if (wid == 11) {
    asm volatile("st.shared.b32 [%0], %1;" ::"r"(sb + OFF_ONES + lane * 4), "r"(0x3F803F80u) : "memory");
    fence_async_smem();
  }

  if (wid >= 8) {
    asm volatile("setmaxnreg.dec.sync.aligned.u32 40;");
    asm volatile("barrier.cluster.arrive.relaxed.aligned;" ::: "memory");
    asm volatile("barrier.cluster.wait.acquire.aligned;" ::: "memory");
    if (wid == 8) {
      if (elect_one()) {
        DBGT(2, 0);
        const uint32_t wdst = sb + OFF_W + rank * 8192;
        const CUtensorMap* tm_gu = rank ? &tm_u : &tm_g;
        auto load_w = [&](int it, const CUtensorMap* tm, int c0, int c1, uint32_t bytes) {
          const int slot = it & 7;
          mbar_wait(bars + (B_WEMPTY + slot) * 8, ((it >> 3) & 1) ^ (slot < 6 ? 1 : 0));
          if ((it & 1) == 0 && it < 54) DBGT(2, 3 + (it >> 1));
          mbar_expect_tx(bars + (B_WFULL + slot) * 8, bytes);
          tma2d_mc(wdst + slot * WSLOT, tm, c0, c1, bars + (B_WFULL + slot) * 8, (uint16_t)3);
        };
#pragma unroll 1
        for (int it = 0; it < 8; it++) {
          if (it == WHOLD) mbar_wait(bars + B_X1GOT * 8, 0);
          load_w(it, &tm_qkv, 512 + 512 * (int)rank + 64 * j, 64 * it, WSLOT);
        }
#pragma unroll 1
        for (int it = 8; it < 24; it++) load_w(it, tm_gu, FS * j + ((it & 16) << 2), 64 * (it & 7), WSLOT);
#pragma unroll 1
        for (int it = 24; it < 28; it++) load_w(it, &tm_qkv, 64 * j, 128 * (it - 24) + 64 * (int)rank, WSLOT);
#pragma unroll 1
        for (int it = 28; it < 36; it++) load_w(it, tm_gu, FS * j + 128, 64 * (it - 28), WSLOT);
        const int c2 = 128 * nu + 64 * (int)rank;
        load_w(36, &tm_d, c2, FS * j, WSLOT);
        load_w(37, &tm_d, c2, FS * j + 64, WSLOT);
        load_w(38, &tm_o, c2, 64 * j, WSLOT);
        load_w(39, &tm_d48, c2, FS * j + 128, 12288);
#pragma unroll 1
        for (int b = 0; b < 5; b++) {
#pragma unroll 1
          for (int p = 0; p < 3; p++) {
            const int jj = peer(p) ^ (b == 3 ? 4 : 0);
            load_w(40 + b * 3 + p, b == 2 ? &tm_o : b >= 3 ? &tm_d48 : &tm_d, c2, b == 2 ? 64 * jj : FS * jj + (b >= 3 ? 128 : 64 * b), b >= 3 ? 12288 : WSLOT);
          }
        }
        DBGT(2, 1);
        atomicAdd(&g_done, 1u);
        DBGT(2, 2);
      }
    } else if (wid <= 10) {
      if (elect_one()) {
        const int w = wid - 9;
        const unsigned tag = get_epoch(sb) + 1;
        const int hm = 2 * m + (w == 0 ? 1 - kap : kap);
        const uint32_t abase = sb + OFF_A + w * NA * ASLOT;
        const uint32_t bfull = bars + (B_AFULL + w * NA) * 8, bempty = bars + (B_AEMPTY + w * NA) * 8, bblk = bars + (B_BLK + w * 4) * 8;
        uint4* a2 = g_a2 + (size_t)(hm * 8 * 3) * (ASLOT / 16);
        uint4* fl = g_flag_a2 + hm * 8;
        uint32_t ready = 0;
        auto poll = [&]() {
          const uint4 a = ld_relaxed_u4(fl + peer(0)), b = ld_relaxed_u4(fl + peer(1)), c = ld_relaxed_u4(fl + peer(2));
          ready = ((a.x == tag && b.x == tag && c.x == tag) ? 1u : 0u) | ((a.y == tag && b.y == tag && c.y == tag) ? 2u : 0u);
        };
        auto load_a = [&](int r) {
          const int p = r % 3, b = r / 3, s = r < 2 ? 4 + r : r == 2 ? 3 : r < 6 ? r - 3 : r < 8 ? r - 2 : 3;
          if (r >= 3) mbar_wait(bempty + s * 8, 0);
          if (w == 1) DBGT(3, 10 + r);
          mbar_expect_tx(bfull + s * 8, ASLOT);
          bulk_load(abase + s * ASLOT, a2 + (size_t)((peer(p) * 3 + b) * (ASLOT / 16)), ASLOT, bfull + s * 8);
        };
#pragma unroll
        for (int b = 0; b < 2; b++) {
          mbar_wait(bblk + b * 8, 0);
          store_block(a2 + (size_t)((j * 3 + b) * (ASLOT / 16)), abase + b * ASLOT, reinterpret_cast<unsigned*>(fl + j) + b, tag);
          if (w == 1) DBGT(3, 4 + b);
          if (w == 1 && b == 0) {
            mbar_expect_tx(bars + B_XFULL * 8, 2 * ASLOT);
            tma2d(abase + 4 * ASLOT, &tm_x, nu * 128, m * 128 + kap * 64, bars + B_XFULL * 8);
            tma2d(abase + 5 * ASLOT, &tm_x, nu * 128 + 64, m * 128 + kap * 64, bars + B_XFULL * 8);
          }
        }
        { uint32_t n = 0; while (!(ready & 1) && ++n < 65536) poll(); }
        if (w == 0) { load_a(0); load_a(1); }
        mbar_wait(bblk + 2 * 8, 0);
        load_a(2);
        { uint32_t n = 0; while (!(ready & 2) && ++n < 65536) poll(); }
        if (w == 1) { mbar_wait(bars + B_X1GO * 8, 0); load_a(0); load_a(1); }
        load_a(3);
        load_a(4);
        load_a(5);
#pragma unroll
        for (int r = 6; r < 9; r++) load_a(r);
        if (w == 1) {
#pragma unroll
          for (int q = 0; q < 6; q++) {
            const int s = q < 3 ? q : q < 5 ? q + 1 : 3;
            mbar_wait(bempty + s * 8, 1);
            DBGT(3, 20 + q);
            mbar_expect_tx(bfull + s * 8, 6144);
            bulk_load(abase + s * ASLOT, g_h2 + (size_t)(hm * 8 + (peer(q % 3) ^ (q < 3 ? 4 : 0))) * 384, 6144, bfull + s * 8);
          }
        }
      }
    } else {
      unsigned epoch = 0;
      if (lane == 0) {
        epoch = ld_relaxed(&g_done) / NCTA;
        asm volatile("st.shared.b32 [%0], %1;" ::"r"(sb + OFF_EPOCH), "r"(epoch) : "memory");
        mbar_arrive(bars + B_EPOCH * 8);
      }
      epoch = __shfl_sync(0xffffffffu, epoch, 0);
      const unsigned tag = epoch + 1;
      if (lane < 17) reinterpret_cast<float4*>(&g_kv[(epoch + 1) & 1][(j * 16 + m) * 68])[lane] = make_float4(0.f, 0.f, 0.f, 0.f);
      if (elect_one()) {
        mbar_wait(bars + B_LAG * 8, 0);
        l2_prefetch(prm.wg + blockIdx.x * 11008, 11008);
        l2_prefetch(prm.wu + blockIdx.x * 11008, 11008);
        mbar_wait(bars + (B_WFULL + 7) * 8, 0);
#pragma unroll
        for (int r = 0; r < 4; r++) l2_prefetch(prm.wqkv + (blockIdx.x * 4 + r) * 3072, 1024);
        l2_prefetch(prm.wd + blockIdx.x * 11008, 11008);
        l2_prefetch(prm.wo + blockIdx.x * 4096, 4096);
#pragma unroll
        for (int w = 0; w < 2; w++) {
          mbar_wait(bars + (B_KVDONE + w) * 8, 0);
          asm volatile("cp.reduce.async.bulk.global.shared::cta.bulk_group.add.f32 [%0], [%1], %2;"
                       ::"l"(&g_kv[epoch & 1][j * 4 * 272]), "r"(sb + OFF_A + (w * NA + 2) * ASLOT), "r"(4 * 272 * 4) : "memory");
        }
        asm volatile("cp.async.bulk.commit_group;" ::: "memory");
        bulk_wait_all();
        fence_async_global();
        red_release_add(&g_cnt_kv[j * 32], 1u);
        DBGT(3, 0);
        poll_ge(&g_cnt_kv[j * 32], 16u * tag);
        DBGT(3, 2);
        mbar_expect_tx(bars + B_KVLD * 8, 4 * 272 * 4);
        bulk_load(sb + OFF_A + 3 * ASLOT + 3072, &g_kv[epoch & 1][j * 4 * 272], 4 * 272 * 4, bars + B_KVLD * 8);
      }
      __syncwarp();
      mbar_wait(bars + B_KVLD * 8, 0);
#pragma unroll
      for (int h = 0; h < 4; h++) {
        const uint32_t src = sb + OFF_A + 3 * ASLOT + 3072 + h * 1088;
        float4 a, b;
        float z0, z1;
        asm volatile("ld.shared.v4.f32 {%0, %1, %2, %3}, [%4];" : "=f"(a.x), "=f"(a.y), "=f"(a.z), "=f"(a.w) : "r"(src + lane * 32) : "memory");
        asm volatile("ld.shared.v4.f32 {%0, %1, %2, %3}, [%4];" : "=f"(b.x), "=f"(b.y), "=f"(b.z), "=f"(b.w) : "r"(src + lane * 32 + 16) : "memory");
        asm volatile("ld.shared.f32 %0, [%1];" : "=f"(z0) : "r"(src + 1024 + (lane >> 2) * 4) : "memory");
        asm volatile("ld.shared.f32 %0, [%1];" : "=f"(z1) : "r"(src + 1056 + (lane >> 2) * 4) : "memory");
        const uint32_t v[6] = {pack_bf16(a.x, a.y), pack_bf16(a.z, a.w), pack_bf16(b.x, b.y),
                               pack_bf16(b.z, b.w), pack_bf16(z0, z0), pack_bf16(z1, z1)};
#pragma unroll
        for (int c = 0; c < 6; c++) {
          const uint32_t dst = sb + OFF_A + 3 * ASLOT + h * 768 + c * 128 + lane * 4;
          asm volatile("st.shared.b32 [%0], %1;" ::"r"(dst), "r"(v[c]) : "memory");
          asm volatile("st.shared.b32 [%0], %1;" ::"r"(dst + NA * ASLOT), "r"(v[c]) : "memory");
        }
      }
      fence_async_smem();
      __syncwarp();
      if (elect_one()) {
        mbar_arrive(bars + B_KVRDY * 8);
        DBGT(3, 3);
      }
      __syncwarp();
      if (elect_one()) {
        const uint4* fl = g_flag_part + (m * 8 + (j ^ 4)) * 8;
        mbar_wait(bars + B_W0DONE * 8, 0);
        uint32_t n = 0;
        while (++n < 65536) {
          const unsigned a = ld_relaxed(&fl[0].x), b = ld_relaxed(&fl[2].x), c = ld_relaxed(&fl[4].x), d = ld_relaxed(&fl[6].x);
          if (a == tag && b == tag && c == tag && d == tag) break;
        }
        DBGT(3, 7);
        mbar_expect_tx(bars + B_PART * 8, 16384);
        bulk_load(sb + OFF_A + 2 * ASLOT, g_part + (size_t)(m * 8 + (j ^ 4)) * (8 * 128), 16384, bars + B_PART * 8);
      }
    }
  } else {
    asm volatile("setmaxnreg.inc.sync.aligned.u32 232;");
    const int w = wid >> 2, wq = wid & 3;
    const uint32_t abase = sb + OFF_A + w * NA * ASLOT;
    const uint32_t laneoff = (uint32_t)((wq * 16 + (lane & 7) + ((lane >> 3) & 1) * 8) * 128 + ((((lane >> 4) ^ lane) & 7) << 4));
    const uint32_t wempty_addr = mapa(bars + B_WEMPTY * 8, lane & 1);
    const uint64_t wofs = (uint64_t)(w * NA * (ASLOT >> 4));
    DBGW(w, 0);
    if (w == 0) DBGG(0);

    uint32_t A[128];
    float rs0, rs1;
    float dl0, dl1;
    {
      float sm[4][4];
#pragma unroll
      for (int i = 0; i < 16; i++) sm[i >> 2][i & 3] = 0.f;
      const uint32_t x67 = sb + OFF_W + (7 - w) * WSLOT;
      asm volatile("barrier.cluster.wait.acquire.aligned;" ::: "memory");
#pragma unroll
      for (int p = 0; p < 4; p++) {
        if (p == 0) asm volatile("cp.async.wait_group 3;" ::: "memory");
        if (p == 1) asm volatile("cp.async.wait_group 2;" ::: "memory");
        if (p == 2) asm volatile("cp.async.wait_group 1;" ::: "memory");
        if (p == 3) asm volatile("cp.async.wait_group 0;" ::: "memory");
        __syncwarp();
        DBGW(w, 20 + p);
        if (lane == 0 && w == WHOLD_W && p == WHOLD_P) mbar_arrive(bars + B_X1GOT * 8);
#pragma unroll
        for (int q = 0; q < 8; q++) {
          const int i = 2 * p + (q >> 2), kk = q & 3;
          ldsm4(&A[(i * 4 + kk) * 4], ((i < 6 ? abase + i * ASLOT : x67 + (i - 6) * ASLOT) + laneoff) ^ (kk << 5));
        }
#pragma unroll
        for (int q = 0; q < 8; q++) mma_rowsum(sm[q & 3], &A[p * 32 + q * 4]);
      }
      if (lane < 2) { mbar_arrive_cluster(wempty_addr + 6 * 8); mbar_arrive_cluster(wempty_addr + 7 * 8); }
      const float s0 = ((sm[0][0] + sm[1][0]) + (sm[2][0] + sm[3][0])) * (1.f / 512.f);
      const float s1 = ((sm[0][2] + sm[1][2]) + (sm[2][2] + sm[3][2])) * (1.f / 512.f);
      const uint32_t m0 = pack_bf16(s0, s0), m1 = pack_bf16(s1, s1);
#pragma unroll 1
      for (unsigned rep = 0; rep < gridDim.y; rep++) {
#pragma unroll
        for (int i = 0; i < 128; i += 2) {
          asm volatile("sub.rn.bf16x2 %0, %0, %1;" : "+r"(A[i]) : "r"(m0));
          asm volatile("sub.rn.bf16x2 %0, %0, %1;" : "+r"(A[i + 1]) : "r"(m1));
        }
      }
      dl0 = s0 - bf_lo(m0); dl1 = s1 - bf_lo(m1);
    }

    {
      float acc[64];
      float q0 = 0.f, q1 = 0.f;
      const uint64_t dB = desc_mn(OFF_W);
      DBGW(w, 1);
      if (w == 1) mbar_wait(bars + B_LAG * 8, 0);
#pragma unroll
      for (int kb = 0; kb <= 8; kb++) {
        if (kb == LAG_KB && w == 0 && lane == 0) mbar_arrive(bars + B_LAG * 8);
        if (kb < 8) {
          mbar_wait_loop(bars + (B_WFULL + kb) * 8, 0);
          WG_FENCE();
#pragma unroll
          for (int kk = 0; kk < 4; kk++)
            wgmma_rs_n128(acc, &A[(kb * 4 + kk) * 4], dB + ((kb * WSLOT + kk * 2048) >> 4), (kb | kk) != 0);
          WG_COMMIT();
          {
            const uint32_t* a = &A[((kb + 2) & 7) * 16];
            uint32_t t0 = 0u, t1 = 0u;
#pragma unroll
            for (int i = 0; i < 16; i += 2) { t0 = bf2_fma(a[i], a[i], t0); t1 = bf2_fma(a[i + 1], a[i + 1], t1); }
            q0 += bf_lo(t0) + bf_hi(t0);
            q1 += bf_lo(t1) + bf_hi(t1);
            asm volatile("" : "+f"(q0), "+f"(q1)::"memory");
          }
        }
        if (kb > 0) {
          if (kb < 8) WG_WAIT(1); else WG_WAIT(0);
          if (lane < 2) mbar_arrive_cluster(wempty_addr + (kb - 1) * 8);
          if (kb == 4) DBGW(w, 24);
        }
      }
      DBGW(w, 2);
      q0 += __shfl_xor_sync(0xffffffffu, q0, 1); q1 += __shfl_xor_sync(0xffffffffu, q1, 1);
      q0 += __shfl_xor_sync(0xffffffffu, q0, 2); q1 += __shfl_xor_sync(0xffffffffu, q1, 2);
      rs0 = rsqrtf(fmaxf(q0 * (1.f / 512.f) - dl0 * dl0, 0.f) + 1e-5f);
      rs1 = rsqrtf(fmaxf(q1 * (1.f / 512.f) - dl1 * dl1, 0.f) + 1e-5f);
      const float rl0 = rs0 * 1.4426950408889634f, rl1 = rs1 * 1.4426950408889634f;
      const uint32_t pk_t = abase + 4 * ASLOT, v_t = abase + 5 * ASLOT;
#pragma unroll
      for (int i = 0; i < 4; i++) {
        const float* c = &acc[8 * i];
        stsm4((pk_t + laneoff) ^ (i << 5),
              pack_bf16(phi(c[0], rl0), phi(c[1], rl0)), pack_bf16(phi(c[2], rl1), phi(c[3], rl1)),
              pack_bf16(phi(c[4], rl0), phi(c[5], rl0)), pack_bf16(phi(c[6], rl1), phi(c[7], rl1)));
        const float* v = &acc[32 + 8 * i];
        stsm4((v_t + laneoff) ^ (i << 5), pack_bf16(v[0] * rs0, v[1] * rs0), pack_bf16(v[2] * rs1, v[3] * rs1),
              pack_bf16(v[4] * rs0, v[5] * rs0), pack_bf16(v[6] * rs1, v[7] * rs1));
      }
      fence_async_smem();
      if (w == 0) asm volatile("bar.sync 1, 128;" ::: "memory"); else asm volatile("bar.sync 2, 128;" ::: "memory");
      DBGW(w, 25);
      float kv[32], zz[4], o8[8];
      WG_FENCE();
#pragma unroll
      for (int ks = 0; ks < 4; ks++) {
        wgmma_st_n64(kv, desc_mn(OFF_A + 4 * ASLOT + ks * 2048) + wofs, desc_mn(OFF_A + 5 * ASLOT + ks * 2048) + wofs, ks != 0);
        wgmma_st_n8(zz, desc_mn(OFF_A + 4 * ASLOT + ks * 2048) + wofs, mkdesc(OFF_ONES, 0, 0, 0), ks != 0);
      }
      WG_COMMIT();
      WG_WAIT(0);
      DBGW(w, 26);
#pragma unroll
      for (int i = 0; i < 8; i++) o8[i] = wq == 0 ? kv[i] : wq == 1 ? kv[8 + i] : wq == 2 ? kv[16 + i] : kv[24 + i];
      const uint32_t kvs = abase + 2 * ASLOT + wq * 1088;
      asm volatile("st.shared.v4.f32 [%0], {%1, %2, %3, %4};" ::"r"(kvs + lane * 32), "f"(o8[0]), "f"(o8[1]), "f"(o8[2]), "f"(o8[3]) : "memory");
      asm volatile("st.shared.v4.f32 [%0], {%1, %2, %3, %4};" ::"r"(kvs + lane * 32 + 16), "f"(o8[4]), "f"(o8[5]), "f"(o8[6]), "f"(o8[7]) : "memory");
      if ((lane & 3) == 0) {
        asm volatile("st.shared.f32 [%0], %1;" ::"r"(kvs + 1024 + lane), "f"(zz[0]) : "memory");
        asm volatile("st.shared.f32 [%0], %1;" ::"r"(kvs + 1056 + lane), "f"(zz[2]) : "memory");
      }
      fence_async_smem();
      __syncwarp();
      if (lane == 0) mbar_arrive(bars + (B_KVDONE + w) * 8);
      DBGW(w, 3);
    }

#pragma unroll 1
    for (int tile = 0; tile < 2; tile++) {
      float acc[64];
      const uint64_t dB = desc_mn(OFF_W);
      PEEK(bars + B_WFULL * 8, tile ^ 1);
#pragma unroll
      for (int kb = 0; kb < 8; kb++) {
        PEEKWAIT(bars + (B_WFULL + kb) * 8, tile ^ 1);
        WG_FENCE();
#pragma unroll
        for (int kk = 0; kk < 4; kk++) {
          wgmma_rs_n128(acc, &A[(kb * 4 + kk) * 4], dB + ((kb * WSLOT + kk * 2048) >> 4), (kb | kk) != 0);
          if (kk == PEEK_AT && kb < 7) PEEK(bars + (B_WFULL + kb + 1) * 8, tile ^ 1);
        }
        WG_COMMIT();
        if (kb > 0) {
          WG_WAIT(1);
          if (lane < 2) mbar_arrive_cluster(wempty_addr + (kb - 1) * 8);
        }
      }
      WG_WAIT(0);
      if (lane < 2) mbar_arrive_cluster(wempty_addr + 7 * 8);
      DBGW(w, 4 + 2 * tile);
      const uint32_t dst = abase + tile * ASLOT + laneoff;
#pragma unroll
      for (int i = 0; i < 4; i++) {
        uint32_t o[4];
#pragma unroll
        for (int q = 0; q < 4; q++) {
          const float cg = (q & 1) ? GC * rs1 : GC * rs0, cv = (q & 1) ? GV * rs1 : GV * rs0;
          const float* c = &acc[8 * i + 2 * q];
          o[q] = pack_bf16(geglu2(c[0] * cg, c[32] * cv), geglu2(c[1] * cg, c[33] * cv));
        }
        stsm4(dst ^ (i << 5), o[0], o[1], o[2], o[3]);
      }
      fence_async_smem();
      __syncwarp();
      if (lane == 0) mbar_arrive(bars + (B_BLK + w * 4 + tile) * 8);
      DBGW(w, 5 + 2 * tile);
    }

    {
      float acc[32];
      const uint64_t dB = desc_mn(OFF_W);
      PEEK(bars + B_WFULL * 8, 1);
#pragma unroll
      for (int kb = 0; kb < 4; kb++) {
        PEEKWAIT(bars + (B_WFULL + kb) * 8, 1);
        WG_FENCE();
#pragma unroll
        for (int kk = 0; kk < 8; kk++) {
          wgmma_rs_n64(acc, &A[(kb * 8 + kk) * 4], dB + ((kb * WSLOT + kk * 2048) >> 4), (kb | kk) != 0);
          if (kk == 2 * PEEK_AT + 1 && kb < 3) PEEK(bars + (B_WFULL + kb + 1) * 8, 1);
        }
        WG_COMMIT();
        if (kb > 0) {
          WG_WAIT(1);
          if (lane < 2) mbar_arrive_cluster(wempty_addr + (kb - 1) * 8);
        }
      }
      WG_WAIT(0);
      if (lane < 2) mbar_arrive_cluster(wempty_addr + 3 * 8);
      DBGW(w, 8);
      const float rl0 = rs0 * 1.4426950408889634f, rl1 = rs1 * 1.4426950408889634f;
      uint32_t pq[16];
#pragma unroll
      for (int h = 0; h < 4; h++) {
        const float* c = &acc[8 * h];
        pq[4 * h + 0] = pack_bf16(phi(c[0], rl0), phi(c[1], rl0));
        pq[4 * h + 1] = pack_bf16(phi(c[2], rl1), phi(c[3], rl1));
        pq[4 * h + 2] = pack_bf16(phi(c[4], rl0), phi(c[5], rl0));
        pq[4 * h + 3] = pack_bf16(phi(c[6], rl1), phi(c[7], rl1));
      }
      mbar_wait(bars + B_KVRDY * 8, 0);
      const uint32_t qtag = (get_epoch(sb) + 1) & 1;
      float nd[4][12];
      WG_FENCE();
#pragma unroll
      for (int h = 0; h < 4; h++) wgmma_rs_n24(nd[h], &pq[4 * h], mkdesc(OFF_A + 3 * ASLOT + h * 768, 128, 256, 0) + wofs, 0);
      WG_COMMIT();
      WG_WAIT(0);
      uint4* op = g_a2 + (size_t)(((2 * m + (w == 0 ? 1 - kap : kap)) * 8 + j) * 3 + 2) * (ASLOT / 16) + (tid & 127);
#pragma unroll
      for (int h = 0; h < 4; h++) {
        const float* n = nd[h];
        const float i0 = rcpf(n[8] + 1e-6f), i1 = rcpf(n[10] + 1e-6f);
        const uint32_t o0 = pack_bf16(n[0] * i0, n[1] * i0), o1 = pack_bf16(n[2] * i1, n[3] * i1), o2 = pack_bf16(n[4] * i0, n[5] * i0),
                       o3 = pack_bf16(n[6] * i1, n[7] * i1);
        stsm4((abase + 2 * ASLOT + laneoff) ^ (h << 5), o0, o1, o2, o3);
        __stcg(op + h * 128, make_uint4((o0 & ~1u) | qtag, o1, o2, o3));
      }
      fence_async_smem();
      __syncwarp();
      if (lane == 0) mbar_arrive(bars + (B_BLK + w * 4 + 2) * 8);
      DBGW(w, 9);
    }

    float ag[24], au[24];
    const uint64_t dB2 = desc_mn(OFF_W);
    PEEK(bars + (B_WFULL + 4) * 8, 1);
#pragma unroll
    for (int kb = 0; kb < 8; kb++) {
      const int slot = (4 + kb) & 7;
      PEEKWAIT(bars + (B_WFULL + slot) * 8, kb < 4 ? 1 : 0);
      WG_FENCE();
#pragma unroll
      for (int kk = 0; kk < 4; kk++) {
        wgmma_rs_n48(ag, &A[(kb * 4 + kk) * 4], dB2 + ((slot * WSLOT + kk * 2048) >> 4), (kb | kk) != 0);
        wgmma_rs_n48(au, &A[(kb * 4 + kk) * 4], dB2 + ((slot * WSLOT + 8192 + kk * 2048) >> 4), (kb | kk) != 0);
        if (kk == PEEK_AT && kb < 7) PEEK(bars + (B_WFULL + ((slot + 1) & 7)) * 8, kb + 1 < 4 ? 1 : 0);
      }
      WG_COMMIT();
      if (kb > 0) {
        WG_WAIT(1);
        if (lane < 2) mbar_arrive_cluster(wempty_addr + ((slot + 7) & 7) * 8);
      }
    }
    WG_WAIT(0);
    if (lane < 2) mbar_arrive_cluster(wempty_addr + 3 * 8);
    DBGW(w, 10);

    const int row_w = m * 128 + (w == 0 ? 1 - kap : kap) * 64 + wq * 16;
    float acc[64];
    const uint32_t bfull = bars + (B_AFULL + w * NA) * 8, bempty = bars + (B_AEMPTY + w * NA) * 8, bblk = bars + (B_BLK + w * 4) * 8;
    const uint64_t dA3 = desc_k(OFF_A) + wofs, dB3 = desc_mn(OFF_W);
    auto a_slot = [&](int e) { const int r = e - 4; return e < 3 ? e : r < 2 ? 4 + r : r == 2 ? 3 : r < 6 ? r - 3 : r < 8 ? r - 2 : 3; };
    auto p2_issue = [&](int e) {
      const int pos = 36 + e, slot = pos & 7, as = a_slot(e);
      mbar_wait(e < 3 ? bblk + e * 8 : bfull + as * 8, e >= 10 ? 1 : 0);
      mbar_wait(bars + (B_WFULL + slot) * 8, (pos >> 3) & 1);
      WG_FENCE();
#pragma unroll
      for (int kk = 0; kk < 4; kk++)
        wgmma_ss_n128(acc, dA3 + ((as * ASLOT + kk * 32) >> 4), dB3 + ((slot * WSLOT + kk * 2048) >> 4), 1);
      WG_COMMIT();
    };
    auto p2_issue_rs = [&](int e, const uint32_t* af, int nk = 3) {
      const int pos = 36 + e, slot = pos & 7;
      mbar_wait(bars + (B_WFULL + slot) * 8, (pos >> 3) & 1);
      WG_FENCE();
#pragma unroll
      for (int kk = 0; kk < nk; kk++) wgmma_rs_n128(acc, &af[kk * 4], dB3 + ((slot * WSLOT + kk * 2048) >> 4), 1);
      WG_COMMIT();
    };
    auto p2_release = [&](int e) {
      const int pos = 36 + e;
      if (e <= 10 && lane < 2) mbar_arrive_cluster(wempty_addr + (pos & 7) * 8);
      if (e <= 9 && e != 3 && lane == 0) mbar_arrive(bempty + a_slot(e) * 8);
    };
    const uint32_t tag = get_epoch(sb) + 1, tagbit = tag & 1;
    const int hm = 2 * m + (w == 0 ? 1 - kap : kap);
    float gs[24], us[24];
#pragma unroll
    for (int i = 0; i < 24; i++) {
      gs[i] = ag[i] * ((i & 2) ? GC * rs1 : GC * rs0);
      us[i] = au[i] * ((i & 2) ? GV * rs1 : GV * rs0);
      asm volatile("" : "+f"(gs[i]), "+f"(us[i])::"memory");
    }
    mbar_wait_loop(bblk, 0);
    if (w == 1) {
      uint32_t xr[32];
      mbar_wait(bars + B_XFULL * 8, 0);
#pragma unroll
      for (int q = 0; q < 8; q++) ldsm4(&xr[4 * q], (abase + (4 + (q >> 2)) * ASLOT + laneoff) ^ ((q & 3) << 5));
#pragma unroll
      for (int q = 0; q < 32; q++) { acc[2 * q] = bf_lo(xr[q]); acc[2 * q + 1] = bf_hi(xr[q]); }
      __syncwarp();
      if (lane == 0) mbar_arrive(bars + B_X1GO * 8);
    } else {
#pragma unroll
      for (int q = 0; q < 64; q++) acc[q] = 0.f;
    }
    p2_issue(0);
    p2_issue(1);
    uint32_t hf[12];
    {
#pragma unroll
      for (int i = 0; i < 12; i++)
        hf[i] = pack_bf16(geglu2(gs[2 * i], us[2 * i]), geglu2(gs[2 * i + 1], us[2 * i + 1]));
      uint4* hp = g_h2 + (size_t)(hm * 8 + j) * 384 + (tid & 127);
#pragma unroll
      for (int i = 0; i < 3; i++) __stcg(hp + i * 128, make_uint4((hf[4 * i] & ~1u) | tagbit, hf[4 * i + 1], hf[4 * i + 2], hf[4 * i + 3]));
      DBGW(w, 11);
    }
    WG_WAIT(1);
    p2_release(0);
    p2_issue(2);
    WG_WAIT(1);
    p2_release(1);
    p2_issue_rs(3, hf);
    WG_WAIT(1);
    p2_release(2);
    uint32_t rf[2][16];
    auto f_slot = [&](int e) { return e < 13 ? a_slot(e) : e < 16 ? e - 13 : e < 18 ? e - 12 : 3; };
    auto fetch_f = [&](int e) {
      uint32_t* r = rf[e & 1];
      mbar_wait(bfull + f_slot(e) * 8, e < 16 ? 1 : 0);
#pragma unroll
      for (int i = 0; i < (e < 13 ? 4 : 3); i++)
        asm volatile("ld.shared.v4.u32 {%0, %1, %2, %3}, [%4];" : "=r"(r[4 * i]), "=r"(r[4 * i + 1]), "=r"(r[4 * i + 2]), "=r"(r[4 * i + 3])
                     : "r"(abase + f_slot(e) * ASLOT + (tid & 127) * 16 + i * 2048) : "memory");
    };
    auto check_f = [&](int e) {
      uint32_t* r = rf[e & 1];
      const int l = e < 13 ? 12 : 8;
      if (!__all_sync(0xffffffffu, ~((r[0] ^ tagbit) | (r[4] ^ tagbit) | (r[8] ^ tagbit) | (r[l] ^ tagbit)) & 1)) {
        const uint4* p = (e < 13 ? g_a2 + (size_t)((hm * 8 + peer(e - 10)) * 3 + 2) * (ASLOT / 16)
                                 : g_h2 + (size_t)(hm * 8 + (peer((e - 13) % 3) ^ (e < 16 ? 4 : 0))) * 384) + (tid & 127);
#pragma unroll 1
        for (int tries = 0; tries < 65536; tries++) {
#pragma unroll
          for (int i = 0; i < (e < 13 ? 4 : 3); i++)
            asm volatile("ld.relaxed.gpu.global.v4.u32 {%0, %1, %2, %3}, [%4];"
                         : "=r"(r[4 * i]), "=r"(r[4 * i + 1]), "=r"(r[4 * i + 2]), "=r"(r[4 * i + 3]) : "l"(p + i * 128) : "memory");
          if (__all_sync(0xffffffffu, ~((r[0] ^ tagbit) | (r[4] ^ tagbit) | (r[8] ^ tagbit) | (r[l] ^ tagbit)) & 1)) break;
        }
      }
      if (e < 13 && lane == 0) mbar_arrive(bempty + f_slot(e) * 8);
    };
#pragma unroll
    for (int e = 4; e < 13; e++) {
      if (e < 10) p2_issue(e);
      else { check_f(e); p2_issue_rs(e, rf[e & 1], 4); }
      WG_WAIT(1);
      p2_release(e - 1);
      if (e >= 9 && e < 12) fetch_f(e + 1);
      if ((e & 3) == 3) DBGW(w, 16 + (e >> 2));
    }
    const uint32_t pbuf = sb + OFF_A + 2 * ASLOT + (tid & 127) * 16;
    if (w == 0) {
      DBGW(w, 12);
      uint4* pp = g_part + (size_t)(m * 8 + j) * (8 * 128) + (tid & 127);
      if (FLAG_AT < 0 && lane < 2)
        asm volatile("st.global.cg.v4.u32 [%0], {%1, %1, %1, %1};" ::"l"(g_flag_part + ((m * 8 + j) * 4 + wq) * 2 + lane), "r"(tag) : "memory");
      WG_WAIT(0);
      if (lane == 0) mbar_arrive(bars + B_W0DONE * 8);
#pragma unroll
      for (int i = 0; i <= 8; i++) {
        if (i == FLAG_AT && lane < 2)
          asm volatile("st.global.cg.v4.u32 [%0], {%1, %1, %1, %1};" ::"l"(g_flag_part + ((m * 8 + j) * 4 + wq) * 2 + lane), "r"(tag) : "memory");
        if (i < 8) {
          const float* c = &acc[8 * i];
          asm volatile("st.global.cg.v4.u32 [%0], {%1, %2, %3, %4};" ::"l"(pp + i * 128), "r"((pack_bf16(c[0], c[1]) & ~1u) | tagbit),
                       "r"(pack_bf16(c[2], c[3])), "r"(pack_bf16(c[4], c[5])), "r"(pack_bf16(c[6], c[7])) : "memory");
        }
      }
      DBGW(w, 13);
    } else {
      uint32_t hr[6][12];
      auto fetch_h = [&](int g) {
#pragma unroll
        for (int q = 3 * g; q < 3 * g + 3; q++) {
          mbar_wait(bfull + f_slot(13 + q) * 8, g == 0 ? 1 : 0);
#pragma unroll
          for (int i = 0; i < 3; i++)
            asm volatile("ld.shared.v4.u32 {%0, %1, %2, %3}, [%4];" : "=r"(hr[q][4 * i]), "=r"(hr[q][4 * i + 1]), "=r"(hr[q][4 * i + 2]), "=r"(hr[q][4 * i + 3])
                         : "r"(abase + f_slot(13 + q) * ASLOT + (tid & 127) * 16 + i * 2048) : "memory");
        }
#pragma unroll 1
        for (int tries = 0; tries < 65536; tries++) {
          uint32_t bad = 0;
#pragma unroll
          for (int q = 3 * g; q < 3 * g + 3; q++) bad |= (hr[q][0] ^ tagbit) | (hr[q][4] ^ tagbit) | (hr[q][8] ^ tagbit);
          if (__all_sync(0xffffffffu, ~bad & 1)) break;
#pragma unroll
          for (int q = 3 * g; q < 3 * g + 3; q++) {
            const uint4* p = g_h2 + (size_t)(hm * 8 + (peer(q % 3) ^ (q < 3 ? 4 : 0))) * 384 + (tid & 127);
#pragma unroll
            for (int i = 0; i < 3; i++)
              asm volatile("ld.relaxed.gpu.global.v4.u32 {%0, %1, %2, %3}, [%4];"
                           : "=r"(hr[q][4 * i]), "=r"(hr[q][4 * i + 1]), "=r"(hr[q][4 * i + 2]), "=r"(hr[q][4 * i + 3]) : "l"(p + i * 128) : "memory");
          }
        }
      };
      fetch_h(0);
      DBGW(w, 19);
#pragma unroll
      for (int e = 13; e < 19; e++) {
        p2_issue_rs(e, hr[e - 13], 3);
        if (e == FETCH_B_AT) fetch_h(1);
      }
      DBGW(w, 12);
      mbar_wait(bars + B_PART * 8, 0);
      DBGW(w, 13);
      uint4 pv[8];
#pragma unroll
      for (int i = 0; i < 8; i++)
        asm volatile("ld.shared.v4.u32 {%0, %1, %2, %3}, [%4];" : "=r"(pv[i].x), "=r"(pv[i].y), "=r"(pv[i].z), "=r"(pv[i].w) : "r"(pbuf + i * 2048) : "memory");
      {
        uint32_t ok = 1;
#pragma unroll
        for (int i = 0; i < 8; i++) ok &= pv[i].x ^ tagbit ^ 1;
        if (!__all_sync(0xffffffffu, ok & 1)) {
          const uint4* pq = g_part + (size_t)(m * 8 + (j ^ 4)) * (8 * 128) + (tid & 127);
#pragma unroll 1
          for (int tries = 0; tries < 65536; tries++) {
            ok = 1;
#pragma unroll
            for (int i = 0; i < 8; i++) { pv[i] = ld_relaxed_u4(pq + i * 128); ok &= pv[i].x ^ tagbit ^ 1; }
            if (__all_sync(0xffffffffu, ok & 1)) break;
          }
        }
      }
      float pf[64];
#pragma unroll
      for (int i = 0; i < 8; i++) {
        pf[8 * i] = bf_lo(pv[i].x); pf[8 * i + 1] = bf_hi(pv[i].x); pf[8 * i + 2] = bf_lo(pv[i].y); pf[8 * i + 3] = bf_hi(pv[i].y);
        pf[8 * i + 4] = bf_lo(pv[i].z); pf[8 * i + 5] = bf_hi(pv[i].z); pf[8 * i + 6] = bf_lo(pv[i].w); pf[8 * i + 7] = bf_hi(pv[i].w);
      }
      WG_WAIT(0);
      const uint32_t ot = abase + 1 * ASLOT + laneoff;
#pragma unroll
      for (int i = 0; i < 8; i++) {
        const float* c = &acc[8 * i];
        const float* p = &pf[8 * i];
        stsm4((ot + (i >> 2) * ASLOT) ^ ((i & 3) << 5), pack_bf16(c[0] + p[0], c[1] + p[1]), pack_bf16(c[2] + p[2], c[3] + p[3]),
              pack_bf16(c[4] + p[4], c[5] + p[5]), pack_bf16(c[6] + p[6], c[7] + p[7]));
      }
      fence_async_smem();
      __syncwarp();
      if (elect_one()) {
        tma2d_store(&tm_out, abase + 1 * ASLOT + wq * 2048, nu * 128, row_w);
        tma2d_store(&tm_out, abase + 2 * ASLOT + wq * 2048, nu * 128 + 64, row_w);
        asm volatile("cp.async.bulk.commit_group;" ::: "memory");
        asm volatile("cp.async.bulk.wait_group.read 0;" ::: "memory");
      }
      DBGW(w, 14);
      DBGG(1);
      if (tid == 128) { DBGL(1); }
    }
  }
}

typedef CUresult (*EncodeFn)(CUtensorMap*, CUtensorMapDataType, cuuint32_t, void*, const cuuint64_t*, const cuuint64_t*,
                             const cuuint32_t*, const cuuint32_t*, CUtensorMapInterleave, CUtensorMapSwizzle,
                             CUtensorMapL2promotion, CUtensorMapFloatOOBfill);

void make_map(EncodeFn enc, CUtensorMap* tm, const void* ptr, int rows, int cols, int box_rows = 64) {
  cuuint64_t gd[2] = {(cuuint64_t)cols, (cuuint64_t)rows};
  cuuint64_t gs[1] = {(cuuint64_t)cols * 2};
  cuuint32_t bd[2] = {64, (cuuint32_t)box_rows};
  cuuint32_t es[2] = {1, 1};
  enc(tm, CU_TENSOR_MAP_DATA_TYPE_BFLOAT16, 2, const_cast<void*>(ptr), gd, gs, bd, es, CU_TENSOR_MAP_INTERLEAVE_NONE,
      CU_TENSOR_MAP_SWIZZLE_128B, L2PROMO, CU_TENSOR_MAP_FLOAT_OOB_FILL_NONE);
}

}

extern "C" void kernel_launch(void* const* d_in, const int* in_sizes, int n_in, void* d_out, int out_size) {
  static EncodeFn enc = nullptr;
  if (!enc) {
    void* fn = nullptr;
    cudaDriverEntryPointQueryResult qr;
    cudaGetDriverEntryPoint("cuTensorMapEncodeTiled", &fn, cudaEnableDefault, &qr);
    enc = (EncodeFn)fn;
    cudaFuncSetAttribute(fused_kernel, cudaFuncAttributeMaxDynamicSharedMemorySize, SMEM_BYTES);
  }
  CUtensorMap tx, tqkv, tg, tu, to, td, td48, tout;
  make_map(enc, &tx, d_in[0], S_, D_);
  make_map(enc, &tqkv, d_in[1], D_, 3 * D_);
  make_map(enc, &to, d_in[2], D_, D_);
  make_map(enc, &tg, d_in[4], D_, F_);
  make_map(enc, &tu, d_in[5], D_, F_);
  make_map(enc, &td, d_in[6], F_, D_);
  make_map(enc, &tout, d_out, S_, D_, 16);
  make_map(enc, &td48, d_in[6], F_, D_, 48);
  Params prm;
  prm.x = (const char*)d_in[0]; prm.wqkv = (const char*)d_in[1]; prm.wo = (const char*)d_in[2]; prm.wg = (const char*)d_in[4];
  prm.wu = (const char*)d_in[5]; prm.wd = (const char*)d_in[6];
  fused_kernel<<<NCTA, 384, SMEM_BYTES>>>(tx, tqkv, tg, tu, to, td, td48, tout, prm);
}
```
